```python
import torch

def _softmax(x, axis=-1):
    return torch.softmax(x, dim=axis)
def _gelu(x):
    return torch.nn.functional.gelu(x, approximate="tanh")
def _silu(x):
    return torch.nn.functional.silu(x)
def _sigmoid(x):
    return torch.sigmoid(x)
def _layernorm(x, axis=-1, eps=1e-5):
    m = x.mean(dim=axis, keepdim=True)
    v = x.var(dim=axis, keepdim=True, unbiased=False)
    return (x - m) / torch.sqrt(v + eps)
def _scatter_add(tgt, idx, src, axis=0):
    return tgt.clone().index_add_(axis, idx, src)
def _segment_sum(src, seg, n):
    out = torch.zeros((n,) + src.shape[1:], dtype=src.dtype)
    return out.index_add_(0, seg, src)
def _pad(x, pw):
    flat = tuple(v for pair in reversed(pw) for v in pair)
    return torch.nn.functional.pad(x, flat)

kernel_name = 'recurrent_scan__ssm_conv_h3__swiglu_ffn__prompt'

def setup_inputs():

    _w = (lambda a: (lambda t: t.to(torch.bfloat16) if t.is_floating_point() else t)(torch.as_tensor(a)))
    def _A_setup():
        B, S, D = 1, 2048, 1024
        ks = 4
        return {
            "q": _w((lambda *s: torch.randn(*s, dtype=torch.bfloat16) * 0.05)(B, S, D)),
            "k": _w((lambda *s: torch.randn(*s, dtype=torch.bfloat16) * 0.2)(B, S, D)),
            "v": _w((lambda *s: torch.randn(*s, dtype=torch.bfloat16) * 0.2)(B, S, D)),
            "shift_k": _w((lambda *s: torch.randn(*s, dtype=torch.bfloat16) * 0.2)(D, ks) * 0.5),
            "ssm_k": _w((lambda *s: torch.randn(*s, dtype=torch.bfloat16) * 0.2)(D, S) * (1.0 / S ** 0.5)),
            "ssm_D": _w((lambda *s: torch.randn(*s, dtype=torch.bfloat16) * 0.2)(D)),
        }
    _A_in = _A_setup()

    def _B_setup():
        B, S, D, F = 1, 2048, 1024, 3584
        return {
            "x": _w((lambda *s: torch.randn(*s, dtype=torch.bfloat16) * 0.05)(B, S, D)),
            "w_gate": _w((lambda *s: torch.randn(*s, dtype=torch.bfloat16) * 0.1)(D, F)),
            "w_up": _w((lambda *s: torch.randn(*s, dtype=torch.bfloat16) * 0.1)(D, F)),
            "w_down": _w((lambda *s: torch.randn(*s, dtype=torch.bfloat16) * 0.1)(F, D)),
        }
    _B_in = _B_setup()

    return {
        "A_q": _A_in["q"],
        "A_k": _A_in["k"],
        "A_v": _A_in["v"],
        "A_shift_k": _A_in["shift_k"],
        "A_ssm_k": _A_in["ssm_k"],
        "A_ssm_D": _A_in["ssm_D"],
        "B_x": _B_in["x"],
        "B_w_gate": _B_in["w_gate"],
        "B_w_up": _B_in["w_up"],
        "B_w_down": _B_in["w_down"],
    }

def reference(A_q, A_k, A_v, A_shift_k, A_ssm_k, A_ssm_D, B_x, B_w_gate, B_w_up, B_w_down):
    def _A_ref(q, k, v, shift_k, ssm_k, ssm_D):
        B, S, D = q.shape
        ks = shift_k.shape[-1]
        k_pad = _pad(k, ((0, 0), (ks - 1, 0), (0, 0)))
        k_shift = torch.zeros_like(k)
        for t in range(ks):
            k_shift = k_shift + k_pad[:, t:t + S, :] * shift_k[:, ks - 1 - t][None, None, :]
        kv = k_shift * v
        L = 2 * S
        kv_pad = _pad(kv, ((0, 0), (0, S), (0, 0)))
        kf_pad = _pad(ssm_k, ((0, 0), (0, S)))
        kv_f = (lambda x, axes=(-2,-1): torch.fft.rfft2(x.float(), dim=axes))(kv_pad[:, None, :, :], axes=(1, 2))
        kf_f = (lambda x, axes=(-2,-1): torch.fft.rfft2(x.float(), dim=axes))(kf_pad[:, None, :], axes=(1, 2))
        kf_f = (lambda x, *d: x.permute(*d))(kf_f, 1, 2, 0)
        y_f = kv_f * kf_f[None, :, :, :]
        y = (lambda x, s, axes=(-2,-1): torch.fft.irfft2(x, s=s, dim=axes).to(torch.bfloat16))(y_f, (1, L), axes=(1, 2))[:, 0, :S, :]
        y = y + kv * ssm_D[None, None, :]
        return q * y

    def _B_ref(x, w_gate, w_up, w_down):
        g = _silu(x @ w_gate)
        u = x @ w_up
        return (g * u) @ w_down

    x = A_q
    xn = _layernorm(x, axis=-1)
    s = _A_ref(xn, A_k, A_v, A_shift_k, A_ssm_k, A_ssm_D)
    g = _silu(_B_ref(xn, B_w_gate, B_w_up, B_w_down))
    return x + s * g
```

```cpp
#include <cuda_runtime.h>
#include <cuda_bf16.h>
#include <cuda.h>
#include <stdint.h>

namespace {

constexpr int S_LEN = 2048, DM = 1024, FF = 3584;
constexpr int NCTA = 132, NCL = 66;
constexpr int G1_NT = 28;
constexpr int G2_KB = 56;

#define CONV_P 5
#define CONV_Q4 16
#define CONV_Q5S 8
#define CONV_Q5D 1
constexpr int N_PCL = 32, N_Q5CL = 24, N_Q4CL = 10;
constexpr int CONV_REM = DM - 2 * N_PCL * CONV_P - 2 * N_Q4CL * CONV_Q4 - 2 * N_Q5CL * CONV_Q5S;
constexpr int N_Q5L = CONV_REM / CONV_Q5D;
static_assert(CONV_REM >= 0 && CONV_REM % CONV_Q5D == 0 && N_Q5L <= 2 * N_Q5CL, "conv split");
__device__ __forceinline__ int conv_phys(int l) { return ((l & 511) >> 7) * 256 + (l >> 9) * 128 + (l & 127); }

constexpr uint32_t G1_STAGE = 49152;
constexpr uint32_t OFF_STG = 196608;
constexpr uint32_t OFF_BAR = 229376;
constexpr uint32_t SMEM_BYTES = OFF_BAR + 1024 + 1024;
constexpr int QP = 260;
constexpr uint32_t CV_UROWS = 136, CV_UBYTES = CV_UROWS * 32, CV_USTRIDE = 4608;
constexpr uint32_t CV_OFF_U = 0, CV_OFF_Q = 9216, CV_QSZ = 8704, CV_OFF_EX = CV_OFF_Q + 2 * CV_QSZ, CV_OFF_D = CV_OFF_EX + 43 * 512, CV_WG_BYTES = 49152;
constexpr uint32_t OFF_CONV = OFF_STG - 2 * CV_WG_BYTES;
static_assert(CV_OFF_D + 512 <= CV_WG_BYTES, "conv smem");
constexpr uint32_t B_G1F = 0, B_G1E = 32, B_CVF = 160, B_STF = 192, B_STE = 208, B_CVH = 328, B_EPOCH = 272, B_EPOCHBAR = 280, B_G1DONE = 288, B_YFULL = 296, B_OFREE = 312;

__device__ __nv_bfloat16 g_xn[S_LEN * DM];
__device__ __nv_bfloat16 g_kvT[DM * S_LEN];
__device__ __nv_bfloat16 g_yT[DM * S_LEN];
__device__ __nv_bfloat16 g_H[S_LEN * FF];
struct Flags { unsigned xn[16]; unsigned kv[8]; unsigned y[8]; unsigned h[16 * 32]; unsigned ticket; };
__device__ Flags g_flags;
struct Params {
  CUtensorMap xnA;
  CUtensorMap wg, wu;
  CUtensorMap hSt;
  CUtensorMap hA;
  CUtensorMap wd;
  CUtensorMap uLd;
  CUtensorMap ySt;
  CUtensorMap xEp;
  CUtensorMap yEp;
  CUtensorMap oSt;
  const __nv_bfloat16 *q, *k, *v, *shift_k, *ssm_k, *ssm_D;
  uint32_t zero;
};

__device__ __forceinline__ uint32_t smem_u32(const void* p) { return (uint32_t)__cvta_generic_to_shared(p); }
__device__ __forceinline__ void wg_fence() { asm volatile("wgmma.fence.sync.aligned;" ::: "memory"); }
__device__ __forceinline__ void wg_commit() { asm volatile("wgmma.commit_group.sync.aligned;" ::: "memory"); }
template <int N> __device__ __forceinline__ void wg_wait() { asm volatile("wgmma.wait_group.sync.aligned %0;" ::"n"(N) : "memory"); }
__device__ __forceinline__ uint64_t mkd(uint32_t lo, uint32_t hi) { uint64_t d; asm("mov.b64 %0, {%1, %2};" : "=l"(d) : "r"(lo), "r"(hi)); return d; }
__device__ __forceinline__ void mbar_init(uint32_t bar, uint32_t cnt) { asm volatile("mbarrier.init.shared::cta.b64 [%0], %1;" ::"r"(bar), "r"(cnt)); }
__device__ __forceinline__ void mbar_arrive(uint32_t bar) { asm volatile("mbarrier.arrive.shared::cta.b64 _, [%0];" ::"r"(bar) : "memory"); }
__device__ __forceinline__ void mbar_arrive_remote(uint32_t bar, uint32_t cta) {
  asm volatile("{\n.reg .b32 ra;\nmapa.shared::cluster.u32 ra, %0, %1;\nmbarrier.arrive.shared::cluster.b64 _, [ra];\n}" ::"r"(bar), "r"(cta) : "memory");
}
__device__ __forceinline__ void mbar_expect_tx(uint32_t bar, uint32_t bytes) { asm volatile("mbarrier.arrive.expect_tx.shared::cta.b64 _, [%0], %1;" ::"r"(bar), "r"(bytes) : "memory"); }
__device__ __forceinline__ bool mbar_try(uint32_t bar, uint32_t parity) {
  uint32_t ok;
  asm volatile("{\n.reg .pred p;\nmbarrier.try_wait.parity.shared::cta.b64 p, [%1], %2;\nselp.u32 %0, 1, 0, p;\n}" : "=r"(ok) : "r"(bar), "r"(parity) : "memory");
  return ok != 0;
}
__device__ __forceinline__ void mbar_wait(uint32_t bar, uint32_t parity) {
  uint32_t n = 0;
  while (!mbar_try(bar, parity)) { if (++n > (1u << 20)) break; }
}
__device__ __forceinline__ uint64_t policy_evict_first() { uint64_t p; asm volatile("createpolicy.fractional.L2::evict_first.b64 %0, 1.0;" : "=l"(p)); return p; }
__device__ __forceinline__ void tma_ld2_h(uint32_t dst, const CUtensorMap* tm, int c0, int c1, uint32_t bar, uint64_t pol) {
  asm volatile("cp.async.bulk.tensor.2d.shared::cluster.global.mbarrier::complete_tx::bytes.L2::cache_hint [%0], [%1, {%3, %4}], [%2], %5;"
               ::"r"(dst), "l"(tm), "r"(bar), "r"(c0), "r"(c1), "l"(pol) : "memory");
}
__device__ __forceinline__ void tma_ld2_mc_h(uint32_t dst, const CUtensorMap* tm, int c0, int c1, uint32_t bar, uint64_t pol) {
  asm volatile("cp.async.bulk.tensor.2d.shared::cluster.global.mbarrier::complete_tx::bytes.multicast::cluster.L2::cache_hint [%0], [%1, {%3, %4}], [%2], %5, %6;"
               ::"r"(dst), "l"(tm), "r"(bar), "r"(c0), "r"(c1), "h"((uint16_t)3), "l"(pol) : "memory");
}
__device__ __forceinline__ uint32_t ldg_stream(const uint32_t* p, uint64_t pol) { uint32_t v; asm volatile("ld.global.nc.L1::no_allocate.L2::cache_hint.b32 %0, [%1], %2;" : "=r"(v) : "l"(p), "l"(pol)); return v; }
__device__ __forceinline__ void tma_ld2(uint32_t dst, const CUtensorMap* tm, int c0, int c1, uint32_t bar) {
  asm volatile("cp.async.bulk.tensor.2d.shared::cluster.global.mbarrier::complete_tx::bytes [%0], [%1, {%3, %4}], [%2];"
               ::"r"(dst), "l"(tm), "r"(bar), "r"(c0), "r"(c1) : "memory");
}
__device__ __forceinline__ void tma_ld3(uint32_t dst, const CUtensorMap* tm, int c0, int c1, int c2, uint32_t bar, uint64_t pol) {
  asm volatile("cp.async.bulk.tensor.3d.shared::cluster.global.mbarrier::complete_tx::bytes.L2::cache_hint [%0], [%1, {%3, %4, %5}], [%2], %6;"
               ::"r"(dst), "l"(tm), "r"(bar), "r"(c0), "r"(c1), "r"(c2), "l"(pol) : "memory");
}
__device__ __forceinline__ void bulk_ld(uint32_t dst, const void* src, uint32_t bytes, uint32_t bar, uint64_t pol) {
  asm volatile("cp.async.bulk.shared::cluster.global.mbarrier::complete_tx::bytes.L2::cache_hint [%0], [%1], %2, [%3], %4;" ::"r"(dst), "l"(src), "r"(bytes), "r"(bar), "l"(pol) : "memory");
}
__device__ __forceinline__ void tma_st2(const CUtensorMap* tm, uint32_t src, int c0, int c1) {
  asm volatile("cp.async.bulk.tensor.2d.global.shared::cta.bulk_group [%0, {%2, %3}], [%1];" ::"l"(tm), "r"(src), "r"(c0), "r"(c1) : "memory");
}
__device__ __forceinline__ void tma_st3(const CUtensorMap* tm, uint32_t src, int c0, int c1, int c2) {
  asm volatile("cp.async.bulk.tensor.3d.global.shared::cta.bulk_group [%0, {%2, %3, %4}], [%1];" ::"l"(tm), "r"(src), "r"(c0), "r"(c1), "r"(c2) : "memory");
}
__device__ __forceinline__ void bulk_commit() { asm volatile("cp.async.bulk.commit_group;" ::: "memory"); }
__device__ __forceinline__ void bulk_wait_read0() { asm volatile("cp.async.bulk.wait_group.read 0;" ::: "memory"); }
__device__ __forceinline__ void bulk_wait0() { asm volatile("cp.async.bulk.wait_group 0;" ::: "memory"); }
__device__ __forceinline__ void fence_async_smem() { asm volatile("fence.proxy.async.shared::cta;" ::: "memory"); }
__device__ __forceinline__ void fence_async_all() { asm volatile("fence.proxy.async.global;" ::: "memory"); }
__device__ __forceinline__ void named_bar(int id, int n) { asm volatile("bar.sync %0, %1;" ::"r"(id), "r"(n) : "memory"); }
__device__ __forceinline__ unsigned ld_acquire(const unsigned* p) { unsigned v; asm volatile("ld.acquire.gpu.global.u32 %0, [%1];" : "=r"(v) : "l"(p) : "memory"); return v; }
__device__ __forceinline__ void red_release(unsigned* p, unsigned v) { asm volatile("red.release.gpu.global.add.u32 [%0], %1;" ::"l"(p), "r"(v) : "memory"); }
__device__ __forceinline__ void wait_flag(const unsigned* p, unsigned target) {
  uint32_t n = 0;
  while ((int)(ld_acquire(p) - target) < 0) { if (++n > (1u << 20)) break; __nanosleep(32); }
}
__device__ __forceinline__ void ldsm_x4(uint32_t a, uint32_t* r) {
  asm volatile("ldmatrix.sync.aligned.m8n8.x4.shared.b16 {%0,%1,%2,%3}, [%4];" : "=r"(r[0]), "=r"(r[1]), "=r"(r[2]), "=r"(r[3]) : "r"(a) : "memory");
}
__device__ __forceinline__ void ldsm_x4_t(uint32_t a, uint32_t* r) {
  asm volatile("ldmatrix.sync.aligned.m8n8.x4.trans.shared.b16 {%0,%1,%2,%3}, [%4];" : "=r"(r[0]), "=r"(r[1]), "=r"(r[2]), "=r"(r[3]) : "r"(a) : "memory");
}
__device__ __forceinline__ void stsm_x4(uint32_t a, const uint32_t* r) {
  asm volatile("stmatrix.sync.aligned.m8n8.x4.shared.b16 [%0], {%1,%2,%3,%4};" ::"r"(a), "r"(r[0]), "r"(r[1]), "r"(r[2]), "r"(r[3]) : "memory");
}
__device__ __forceinline__ void stsm_x4_t(uint32_t a, const uint32_t* r) {
  asm volatile("stmatrix.sync.aligned.m8n8.x4.trans.shared.b16 [%0], {%1,%2,%3,%4};" ::"r"(a), "r"(r[0]), "r"(r[1]), "r"(r[2]), "r"(r[3]) : "memory");
}
__device__ __forceinline__ uint32_t lds32(uint32_t a) { uint32_t v; asm volatile("ld.shared.b32 %0, [%1];" : "=r"(v) : "r"(a) : "memory"); return v; }
__device__ __forceinline__ uint32_t pack_bf16(float lo, float hi) { uint32_t r; asm("cvt.rn.bf16x2.f32 %0, %1, %2;" : "=r"(r) : "f"(hi), "f"(lo)); return r; }
__device__ __forceinline__ float bf_lo(uint32_t x) { return __uint_as_float(x << 16); }
__device__ __forceinline__ float bf_hi(uint32_t x) { return __uint_as_float(x & 0xffff0000u); }
__device__ __forceinline__ uint32_t bmul2(uint32_t a, uint32_t b) { __nv_bfloat162 r = __hmul2_rn(*(__nv_bfloat162*)&a, *(__nv_bfloat162*)&b); return *(uint32_t*)&r; }
__device__ __forceinline__ uint32_t badd2(uint32_t a, uint32_t b) { __nv_bfloat162 r = __hadd2_rn(*(__nv_bfloat162*)&a, *(__nv_bfloat162*)&b); return *(uint32_t*)&r; }

__device__ __forceinline__ void silu4(const uint32_t* gb, uint32_t* o) {
#pragma unroll
  for (int q = 0; q < 4; q++) {
    const float h0 = bf_lo(gb[q]) * 0.5f, h1 = bf_hi(gb[q]) * 0.5f;
    float t0, t1;
    asm("tanh.approx.f32 %0, %1;" : "=f"(t0) : "f"(h0));
    asm("tanh.approx.f32 %0, %1;" : "=f"(t1) : "f"(h1));
    o[q] = pack_bf16(fmaf(h0, t0, h0), fmaf(h1, t1, h1));
  }
}

__device__ __forceinline__ void wgmma_ss_n256(float* d, uint64_t da, uint64_t db, int scale_d) {
  asm volatile("{\n.reg .pred p;\nsetp.ne.b32 p, %130, 0;\n"
    "wgmma.mma_async.sync.aligned.m64n256k16.f32.bf16.bf16 {%0, %1, %2, %3, %4, %5, %6, %7, %8, %9, %10, %11, %12, %13, %14, %15, %16, %17, %18, %19, %20, %21, %22, %23, %24, %25, %26, %27, %28, %29, %30, %31, %32, %33, %34, %35, %36, %37, %38, %39, %40, %41, %42, %43, %44, %45, %46, %47, %48, %49, %50, %51, %52, %53, %54, %55, %56, %57, %58, %59, %60, %61, %62, %63, %64, %65, %66, %67, %68, %69, %70, %71, %72, %73, %74, %75, %76, %77, %78, %79, %80, %81, %82, %83, %84, %85, %86, %87, %88, %89, %90, %91, %92, %93, %94, %95, %96, %97, %98, %99, %100, %101, %102, %103, %104, %105, %106, %107, %108, %109, %110, %111, %112, %113, %114, %115, %116, %117, %118, %119, %120, %121, %122, %123, %124, %125, %126, %127}, %128, %129, p, 1, 1, 0, 1;\n}\n"
    : "+f"(d[0]), "+f"(d[1]), "+f"(d[2]), "+f"(d[3]), "+f"(d[4]), "+f"(d[5]), "+f"(d[6]), "+f"(d[7]), "+f"(d[8]), "+f"(d[9]), "+f"(d[10]), "+f"(d[11]), "+f"(d[12]), "+f"(d[13]), "+f"(d[14]), "+f"(d[15]), "+f"(d[16]), "+f"(d[17]), "+f"(d[18]), "+f"(d[19]), "+f"(d[20]), "+f"(d[21]), "+f"(d[22]), "+f"(d[23]), "+f"(d[24]), "+f"(d[25]), "+f"(d[26]), "+f"(d[27]), "+f"(d[28]), "+f"(d[29]), "+f"(d[30]), "+f"(d[31]), "+f"(d[32]), "+f"(d[33]), "+f"(d[34]), "+f"(d[35]), "+f"(d[36]), "+f"(d[37]), "+f"(d[38]), "+f"(d[39]), "+f"(d[40]), "+f"(d[41]), "+f"(d[42]), "+f"(d[43]), "+f"(d[44]), "+f"(d[45]), "+f"(d[46]), "+f"(d[47]), "+f"(d[48]), "+f"(d[49]), "+f"(d[50]), "+f"(d[51]), "+f"(d[52]), "+f"(d[53]), "+f"(d[54]), "+f"(d[55]), "+f"(d[56]), "+f"(d[57]), "+f"(d[58]), "+f"(d[59]), "+f"(d[60]), "+f"(d[61]), "+f"(d[62]), "+f"(d[63]), "+f"(d[64]), "+f"(d[65]), "+f"(d[66]), "+f"(d[67]), "+f"(d[68]), "+f"(d[69]), "+f"(d[70]), "+f"(d[71]), "+f"(d[72]), "+f"(d[73]), "+f"(d[74]), "+f"(d[75]), "+f"(d[76]), "+f"(d[77]), "+f"(d[78]), "+f"(d[79]), "+f"(d[80]), "+f"(d[81]), "+f"(d[82]), "+f"(d[83]), "+f"(d[84]), "+f"(d[85]), "+f"(d[86]), "+f"(d[87]), "+f"(d[88]), "+f"(d[89]), "+f"(d[90]), "+f"(d[91]), "+f"(d[92]), "+f"(d[93]), "+f"(d[94]), "+f"(d[95]), "+f"(d[96]), "+f"(d[97]), "+f"(d[98]), "+f"(d[99]), "+f"(d[100]), "+f"(d[101]), "+f"(d[102]), "+f"(d[103]), "+f"(d[104]), "+f"(d[105]), "+f"(d[106]), "+f"(d[107]), "+f"(d[108]), "+f"(d[109]), "+f"(d[110]), "+f"(d[111]), "+f"(d[112]), "+f"(d[113]), "+f"(d[114]), "+f"(d[115]), "+f"(d[116]), "+f"(d[117]), "+f"(d[118]), "+f"(d[119]), "+f"(d[120]), "+f"(d[121]), "+f"(d[122]), "+f"(d[123]), "+f"(d[124]), "+f"(d[125]), "+f"(d[126]), "+f"(d[127])
    : "l"(da), "l"(db), "r"(scale_d));
}
__device__ __forceinline__ void wgmma_rs_n128(float* d, const uint32_t* a, uint64_t db, int scale_d) {
  asm volatile("{\n.reg .pred p;\nsetp.ne.b32 p, %69, 0;\n"
    "wgmma.mma_async.sync.aligned.m64n128k16.f32.bf16.bf16 {%0, %1, %2, %3, %4, %5, %6, %7, %8, %9, %10, %11, %12, %13, %14, %15, %16, %17, %18, %19, %20, %21, %22, %23, %24, %25, %26, %27, %28, %29, %30, %31, %32, %33, %34, %35, %36, %37, %38, %39, %40, %41, %42, %43, %44, %45, %46, %47, %48, %49, %50, %51, %52, %53, %54, %55, %56, %57, %58, %59, %60, %61, %62, %63}, {%64, %65, %66, %67}, %68, p, 1, 1, 0;\n}\n"
    : "+f"(d[0]), "+f"(d[1]), "+f"(d[2]), "+f"(d[3]), "+f"(d[4]), "+f"(d[5]), "+f"(d[6]), "+f"(d[7]), "+f"(d[8]), "+f"(d[9]), "+f"(d[10]), "+f"(d[11]), "+f"(d[12]), "+f"(d[13]), "+f"(d[14]), "+f"(d[15]), "+f"(d[16]), "+f"(d[17]), "+f"(d[18]), "+f"(d[19]), "+f"(d[20]), "+f"(d[21]), "+f"(d[22]), "+f"(d[23]), "+f"(d[24]), "+f"(d[25]), "+f"(d[26]), "+f"(d[27]), "+f"(d[28]), "+f"(d[29]), "+f"(d[30]), "+f"(d[31]), "+f"(d[32]), "+f"(d[33]), "+f"(d[34]), "+f"(d[35]), "+f"(d[36]), "+f"(d[37]), "+f"(d[38]), "+f"(d[39]), "+f"(d[40]), "+f"(d[41]), "+f"(d[42]), "+f"(d[43]), "+f"(d[44]), "+f"(d[45]), "+f"(d[46]), "+f"(d[47]), "+f"(d[48]), "+f"(d[49]), "+f"(d[50]), "+f"(d[51]), "+f"(d[52]), "+f"(d[53]), "+f"(d[54]), "+f"(d[55]), "+f"(d[56]), "+f"(d[57]), "+f"(d[58]), "+f"(d[59]), "+f"(d[60]), "+f"(d[61]), "+f"(d[62]), "+f"(d[63])
    : "r"(a[0]), "r"(a[1]), "r"(a[2]), "r"(a[3]), "l"(db), "r"(scale_d));
}
__device__ __forceinline__ void wgmma_rs_n96(float* d, const uint32_t* a, uint64_t db, int scale_d) {
  asm volatile("{\n.reg .pred p;\nsetp.ne.b32 p, %53, 0;\n"
    "wgmma.mma_async.sync.aligned.m64n96k16.f32.bf16.bf16 {%0, %1, %2, %3, %4, %5, %6, %7, %8, %9, %10, %11, %12, %13, %14, %15, %16, %17, %18, %19, %20, %21, %22, %23, %24, %25, %26, %27, %28, %29, %30, %31, %32, %33, %34, %35, %36, %37, %38, %39, %40, %41, %42, %43, %44, %45, %46, %47}, {%48, %49, %50, %51}, %52, p, 1, 1, 0;\n}\n"
    : "+f"(d[0]), "+f"(d[1]), "+f"(d[2]), "+f"(d[3]), "+f"(d[4]), "+f"(d[5]), "+f"(d[6]), "+f"(d[7]), "+f"(d[8]), "+f"(d[9]), "+f"(d[10]), "+f"(d[11]), "+f"(d[12]), "+f"(d[13]), "+f"(d[14]), "+f"(d[15]), "+f"(d[16]), "+f"(d[17]), "+f"(d[18]), "+f"(d[19]), "+f"(d[20]), "+f"(d[21]), "+f"(d[22]), "+f"(d[23]), "+f"(d[24]), "+f"(d[25]), "+f"(d[26]), "+f"(d[27]), "+f"(d[28]), "+f"(d[29]), "+f"(d[30]), "+f"(d[31]), "+f"(d[32]), "+f"(d[33]), "+f"(d[34]), "+f"(d[35]), "+f"(d[36]), "+f"(d[37]), "+f"(d[38]), "+f"(d[39]), "+f"(d[40]), "+f"(d[41]), "+f"(d[42]), "+f"(d[43]), "+f"(d[44]), "+f"(d[45]), "+f"(d[46]), "+f"(d[47])
    : "r"(a[0]), "r"(a[1]), "r"(a[2]), "r"(a[3]), "l"(db), "r"(scale_d));
}
__device__ __forceinline__ void wgmma_rs_n64(float* d, const uint32_t* a, uint64_t db, int scale_d) {
  asm volatile("{\n.reg .pred p;\nsetp.ne.b32 p, %37, 0;\n"
    "wgmma.mma_async.sync.aligned.m64n64k16.f32.bf16.bf16 {%0, %1, %2, %3, %4, %5, %6, %7, %8, %9, %10, %11, %12, %13, %14, %15, %16, %17, %18, %19, %20, %21, %22, %23, %24, %25, %26, %27, %28, %29, %30, %31}, {%32, %33, %34, %35}, %36, p, 1, 1, 0;\n}\n"
    : "+f"(d[0]), "+f"(d[1]), "+f"(d[2]), "+f"(d[3]), "+f"(d[4]), "+f"(d[5]), "+f"(d[6]), "+f"(d[7]), "+f"(d[8]), "+f"(d[9]), "+f"(d[10]), "+f"(d[11]), "+f"(d[12]), "+f"(d[13]), "+f"(d[14]), "+f"(d[15]), "+f"(d[16]), "+f"(d[17]), "+f"(d[18]), "+f"(d[19]), "+f"(d[20]), "+f"(d[21]), "+f"(d[22]), "+f"(d[23]), "+f"(d[24]), "+f"(d[25]), "+f"(d[26]), "+f"(d[27]), "+f"(d[28]), "+f"(d[29]), "+f"(d[30]), "+f"(d[31])
    : "r"(a[0]), "r"(a[1]), "r"(a[2]), "r"(a[3]), "l"(db), "r"(scale_d));
}
__device__ __forceinline__ void wgmma_rs_n32(float* d, const uint32_t* a, uint64_t db, int scale_d) {
  asm volatile("{\n.reg .pred p;\nsetp.ne.b32 p, %21, 0;\n"
    "wgmma.mma_async.sync.aligned.m64n32k16.f32.bf16.bf16 {%0, %1, %2, %3, %4, %5, %6, %7, %8, %9, %10, %11, %12, %13, %14, %15}, {%16, %17, %18, %19}, %20, p, 1, 1, 0;\n}\n"
    : "+f"(d[0]), "+f"(d[1]), "+f"(d[2]), "+f"(d[3]), "+f"(d[4]), "+f"(d[5]), "+f"(d[6]), "+f"(d[7]), "+f"(d[8]), "+f"(d[9]), "+f"(d[10]), "+f"(d[11]), "+f"(d[12]), "+f"(d[13]), "+f"(d[14]), "+f"(d[15])
    : "r"(a[0]), "r"(a[1]), "r"(a[2]), "r"(a[3]), "l"(db), "r"(scale_d));
}

#define CPY(dst, src, off, n) _Pragma("unroll") for (int i_ = 0; i_ < n; i_++) { asm volatile("mov.b32 %0, %1;" : "=f"(dst[i_]) : "f"(src[i_ + off])); }

template <int J> __device__ __forceinline__ void conv_group(float* acc, const uint32_t (*a)[4], uint32_t ulo) {
#pragma unroll
  for (int sg = 0; sg < 8; sg++) {
    uint64_t db = mkd(ulo + (((8 - sg) * 32) >> 4), 0xC0000010u);
    int sc = (J == 0 && sg == 0) ? 0 : 1;
    if (J == 0) wgmma_rs_n128(acc, a[sg], db, sc);
    if (J == 1) wgmma_rs_n96(acc, a[sg], db, sc);
    if (J == 2) wgmma_rs_n64(acc, a[sg], db, sc);
    if (J == 3) wgmma_rs_n32(acc, a[sg], db, sc);
  }
}
template <int J> __device__ __forceinline__ void conv_load_t(uint32_t* t, uint32_t qaddr) {
#pragma unroll
  for (int q = 0; q < 17; q++) t[q] = lds32(qaddr + (64 * J + q) * 4);
}
__device__ __forceinline__ void conv_expand_a(uint32_t (*a)[4], const uint32_t* t, uint32_t zero) {
  uint32_t ck; asm volatile("mov.u32 %0, %%clock;" : "=r"(ck));
  const uint32_t z = ck & zero;
#pragma unroll
  for (int sg = 0; sg < 8; sg++) {
    a[sg][0] = t[2 * sg + 1];
    a[sg][1] = t[2 * sg + 2];
    if (sg == 0) a[sg][2] = t[0]; else asm volatile("xor.b32 %0, %1, %2;" : "=r"(a[sg][2]) : "r"(t[2 * sg]), "r"(z));
    asm volatile("xor.b32 %0, %1, %2;" : "=r"(a[sg][3]) : "r"(t[2 * sg + 1]), "r"(z));
  }
}
__host__ __device__ constexpr int conv_slot(int bo, int w) { return (bo >= 4 ? 6 + 3 * (bo - 4) : bo * (bo - 1) / 2) + (w < bo / 4 ? w : w - 1); }
template <int W> __device__ __forceinline__ void conv_send(const float* c0, const float* c1, const float* c2, const float* c3, uint32_t exl, float* own, uint32_t zero) {
#pragma unroll
  for (int b = 0; b < 16; b++) {
    const float* src = (b < 4 ? c0 : b < 8 ? c1 : b < 12 ? c2 : c3) + 4 * (b & 3);
    const int bo = b + W;
    if (bo < 16) {
      if (bo / 4 == W) {
#pragma unroll
        for (int k = 0; k < 4; k++) { uint32_t o_; asm volatile("xor.b32 %0, %1, %2;" : "=r"(o_) : "r"(__float_as_uint(src[k])), "r"(zero)); own[4 * (bo & 3) + k] = __uint_as_float(o_); }
      } else {
        const uint32_t rr[4] = {__float_as_uint(src[0]), __float_as_uint(src[1]), __float_as_uint(src[2]), __float_as_uint(src[3])};
        stsm_x4(exl + conv_slot(bo, W) * 512, rr);
      }
    }
  }
}
__device__ __forceinline__ void conv_recv(uint32_t exl, int w, float* y) {
  const uint32_t exw = exl + (12 * w - 6) * 512;
#pragma unroll
  for (int h = 0; h < 2; h++) {
    uint32_t rr[6][4];
#pragma unroll
    for (int i = 0; i < 2; i++)
#pragma unroll
      for (int k = 0; k < 3; k++) {
        const int ii = 2 * h + i;
        const uint32_t a0 = exl + (k < ii ? ii * (ii - 1) / 2 + k : 42) * 512;
        ldsm_x4(w == 0 ? a0 : exw + (3 * ii + k) * 512, rr[3 * i + k]);
      }
#pragma unroll
    for (int i = 0; i < 2; i++)
#pragma unroll
      for (int k = 0; k < 4; k++)
        y[4 * (2 * h + i) + k] += (__uint_as_float(rr[3 * i][k]) + __uint_as_float(rr[3 * i + 1][k])) + __uint_as_float(rr[3 * i + 2][k]);
  }
}
__device__ __forceinline__ void conv_build_q(uint32_t qb, uint32_t hraw, int tid) {
  uint4 h0, h1; uint32_t prev = 0;
  asm volatile("ld.shared.v4.b32 {%0, %1, %2, %3}, [%4];" : "=r"(h0.x), "=r"(h0.y), "=r"(h0.z), "=r"(h0.w) : "r"(hraw + tid * 32) : "memory");
  asm volatile("ld.shared.v4.b32 {%0, %1, %2, %3}, [%4];" : "=r"(h1.x), "=r"(h1.y), "=r"(h1.z), "=r"(h1.w) : "r"(hraw + tid * 32 + 16) : "memory");
  if (tid > 0) prev = lds32(hraw + tid * 32 - 4);
  uint32_t wd[8] = {h0.x, h0.y, h0.z, h0.w, h1.x, h1.y, h1.z, h1.w};
  uint32_t P[16];
#pragma unroll
  for (int e = 0; e < 8; e++) {
    P[2 * e] = __byte_perm(wd[e], prev, 0x7610);
    P[2 * e + 1] = __byte_perm(wd[e], 0, 0x1032);
    prev = wd[e];
  }
#pragma unroll
  for (int rr = 0; rr < 8; rr++) {
    uint32_t ad = qb + (rr * QP + 4 + 2 * tid) * 4;
    asm volatile("st.shared.v2.b32 [%0], {%1, %2};" ::"r"(ad), "r"(P[rr]), "r"(P[8 + rr]) : "memory");
  }
}

__device__ __forceinline__ void kernel_tail() {
}

__global__ void __cluster_dims__(2, 1, 1) __launch_bounds__(384, 1)
h3_ffn_kernel(const __grid_constant__ Params p, __nv_bfloat16* __restrict__ out) {
  extern __shared__ __align__(1024) uint8_t smem_raw[];
  const uint32_t sb = (smem_u32(smem_raw) + 1023) & ~1023u;
  const uint32_t bar = sb + OFF_BAR;
  const int warp = __shfl_sync(0xffffffffu, threadIdx.x >> 5, 0);
  const int lane = threadIdx.x & 31;
  const int bid = blockIdx.x;
  const int cid = bid >> 1;
  const uint32_t rank = bid & 1;
  const bool has_g2 = cid < N_PCL;
  const int n_g1 = has_g2 ? 2 : (cid < N_PCL + N_Q5CL ? 5 : 4);
  const int g2_n = cid >> 3;
  const int g2_m = 2 * (cid & 7) + rank;
  int cv_start, cv_cnt;
  if (has_g2) { cv_cnt = CONV_P; cv_start = bid * CONV_P; }
  else if (cid >= N_PCL + N_Q5CL) { cv_cnt = CONV_Q4; cv_start = 2 * N_PCL * CONV_P + (bid - 2 * (N_PCL + N_Q5CL)) * CONV_Q4; }
  else {
    const int j = bid - 2 * N_PCL, ns = 2 * N_Q5CL - N_Q5L;
    cv_cnt = CONV_Q5S + (j < ns ? 0 : CONV_Q5D);
    cv_start = 2 * N_PCL * CONV_P + 2 * N_Q4CL * CONV_Q4 + j * CONV_Q5S + (j < ns ? 0 : CONV_Q5D * (j - ns));
  }
  auto g1_tile = [&](int i) { return i < 2 ? cid + NCL * i : 2 * NCL + (NCL - N_PCL) * (i - 2) + (cid - N_PCL); };

  uint4 xv[2][4];
  if (warp >= 4 && bid < 128) {
    const int row0 = bid * 16 + (warp - 4) * 2;
#pragma unroll
    for (int rr = 0; rr < 2; rr++)
#pragma unroll
      for (int j = 0; j < 4; j++) xv[rr][j] = __ldg((const uint4*)(p.q + (size_t)(row0 + rr) * DM + j * 256 + lane * 8));
  }
  if (threadIdx.x == 32) {
    const CUtensorMap* tms[4] = {&p.xnA, &p.wg, &p.wu, &p.hSt};
    for (int i = 0; i < 4; i++) asm volatile("prefetch.tensormap [%0];" ::"l"(tms[i]) : "memory");
  }
  if (threadIdx.x == 0) {
    for (int s = 0; s < 4; s++) { mbar_init(bar + B_G1F + s * 8, 1); mbar_init(bar + B_G1E + s * 8, 4); }
    for (int s = 0; s < 4; s++) mbar_init(bar + B_CVF + s * 8, 1);
    for (int s = 0; s < 6; s++) mbar_init(bar + B_CVH + s * 8, 1);
    for (int s = 0; s < 2; s++) { mbar_init(bar + B_STF + s * 8, 128); mbar_init(bar + B_STE + s * 8, 1); }
    mbar_init(bar + B_EPOCHBAR, 1);
    mbar_init(bar + B_G1DONE, 2);
    for (int s = 0; s < 2; s++) { mbar_init(bar + B_YFULL + s * 8, 128); mbar_init(bar + B_OFREE + s * 8, 1); }
    asm volatile("fence.mbarrier_init.release.cluster;" ::: "memory");
  }
  __syncthreads();
  asm volatile("barrier.cluster.arrive.relaxed.aligned;" ::: "memory");
  unsigned ticket = 0;
  if (threadIdx.x == 0) ticket = atomicAdd(&g_flags.ticket, 1u);
  asm volatile("barrier.cluster.wait.aligned;" ::: "memory");
  auto get_ep = [&]() { mbar_wait(bar + B_EPOCHBAR, 0); return lds32(bar + B_EPOCH); };

  if (warp < 4) {
    asm volatile("setmaxnreg.dec.sync.aligned.u32 56;");
    if (warp == 0) {
      int st = 0; uint32_t ph = 1;
      const uint64_t pol = policy_evict_first();
      unsigned ep = 0;
      for (int i = 0; i < n_g1; i++) {
        const int pt = g1_tile(i);
        const int n = pt >> 3, m = 2 * (pt & 7) + rank;
        const CUtensorMap* wmap = rank ? &p.wu : &p.wg;
        if (lane == 0) {
          if (i == 0) {
            for (int kb = 0; kb < 4; kb++) {
              uint32_t sa = sb + kb * G1_STAGE, fb = bar + B_G1F + kb * 8;
              mbar_expect_tx(fb, G1_STAGE);
              tma_ld2_mc_h(sa + 16384 + rank * 16384, wmap, n * 128, kb * 64, fb, pol);
              tma_ld2_mc_h(sa + 16384 + rank * 16384 + 8192, wmap, n * 128 + 64, kb * 64, fb, pol);
            }
            ep = ticket / NCTA + 1u;
            asm volatile("st.shared.b32 [%0], %1;" ::"r"(bar + B_EPOCH), "r"(ep) : "memory");
            mbar_arrive(bar + B_EPOCHBAR);
            wait_flag(&g_flags.xn[m], 8 * ep);
            fence_async_all();
            for (int kb = 0; kb < 4; kb++) tma_ld2(sb + kb * G1_STAGE, &p.xnA, kb * 64, m * 128, bar + B_G1F + kb * 8);
            ph = 0;
          } else {
            wait_flag(&g_flags.xn[m], 8 * ep);
            fence_async_all();
          }
          for (int kb = (i == 0 ? 4 : 0); kb < 16; kb++) {
            mbar_wait(bar + B_G1E + st * 8, ph);
            uint32_t sa = sb + st * G1_STAGE, fb = bar + B_G1F + st * 8;
            mbar_expect_tx(fb, G1_STAGE);
            tma_ld2(sa, &p.xnA, kb * 64, m * 128, fb);
            tma_ld2_mc_h(sa + 16384 + rank * 16384, wmap, n * 128, kb * 64, fb, pol);
            tma_ld2_mc_h(sa + 16384 + rank * 16384 + 8192, wmap, n * 128 + 64, kb * 64, fb, pol);
            if (++st == 4) { st = 0; ph ^= 1; }
          }
        }
        __syncwarp();
      }
      if (has_g2) {
        st = __shfl_sync(0xffffffffu, st, 0); ph = __shfl_sync(0xffffffffu, ph, 0);
        ep = __shfl_sync(0xffffffffu, ep, 0);
        uint32_t ready = 0;
        uint32_t yready = 0;
        for (int kb = 0; kb < G2_KB + 4; kb++) {
          if (kb == G2_KB - 8 && lane < 8) {
            const CUtensorMap* tm = lane < 4 ? &p.xEp : &p.xnA;
            asm volatile("cp.async.bulk.prefetch.tensor.2d.L2.global [%0, {%1, %2}];" ::"l"(tm), "r"(g2_n * 256 + (lane & 3) * 64), "r"(g2_m * 128) : "memory");
          }
          if (kb < G2_KB) {
            const int need = kb >> 1;
            uint32_t spin = 0;
            const bool poll = !((ready >> need) & 1);
            while (!((ready >> need) & 1)) {
              unsigned f = lane < G1_NT ? ld_acquire(&g_flags.h[g2_m * 32 + lane]) : 0u;
              ready = __ballot_sync(0xffffffffu, lane < G1_NT && (int)(f - 2 * ep) >= 0);
              if (++spin > (1u << 20)) break;
              if (!((ready >> need) & 1)) __nanosleep(64);
            }
            if (poll) fence_async_all();
          } else if (!(kb & 1)) {
            const int hf = (kb - G2_KB) >> 1;
            if (!((yready >> hf) & 1)) {
              uint32_t spin = 0;
              while (!((yready >> hf) & 1)) {
                unsigned f = lane < 2 ? ld_acquire(&g_flags.y[2 * g2_n + lane]) : 0u;
                yready = __ballot_sync(0xffffffffu, lane < 2 && (int)(f - 128 * ep) >= 0);
                if (++spin > (1u << 20)) break;
              }
              fence_async_all();
            }
          }
          __syncwarp();
          if (lane == 0) {
            mbar_wait(bar + B_G1E + st * 8, ph);
            const uint32_t sa = sb + st * G1_STAGE, fb = bar + B_G1F + st * 8;
            mbar_expect_tx(fb, G1_STAGE);
            if (kb < G2_KB) {
              tma_ld2_h(sa, &p.hA, kb * 64, g2_m * 128, fb, pol);
              tma_ld2_mc_h(sa + 16384 + rank * 16384, &p.wd, g2_n * 256 + rank * 128, kb * 64, fb, pol);
              tma_ld2_mc_h(sa + 16384 + rank * 16384 + 8192, &p.wd, g2_n * 256 + rank * 128 + 64, kb * 64, fb, pol);
            } else {
              const int hf = (kb - G2_KB) >> 1, which = kb & 1;
              const CUtensorMap* tm = which ? &p.xnA : &p.xEp;
              tma_ld2(sa, tm, g2_n * 256 + hf * 128, g2_m * 128, fb);
              tma_ld2(sa + 16384, tm, g2_n * 256 + hf * 128 + 64, g2_m * 128, fb);
              tma_ld2(sa + 32768, &p.yEp, g2_m * 128 + which * 64, g2_n * 256 + hf * 128, fb);
            }
          }
          if (++st == 4) { st = 0; ph ^= 1; }
          __syncwarp();
        }
      }
    } else {
      if (bid < 128) {
        if (lane == 0) wait_flag(&g_flags.xn[bid >> 3], 8 * get_ep());
        __syncwarp();
        const int tb = bid >> 3, db = bid & 7;
        const uint64_t pol = policy_evict_first();
        for (int wi = warp - 1; wi < 16; wi += 3) {
          const int d0 = db * 128 + (wi & 1) * 64 + 2 * lane;
          const int t0 = tb * 128 + (wi >> 1) * 16;
          const uint2 sa = __ldg((const uint2*)(p.shift_k + d0 * 4));
          const uint2 sbq = __ldg((const uint2*)(p.shift_k + d0 * 4 + 4));
          const uint32_t s0 = __byte_perm(sa.x, sbq.x, 0x5410), s1 = __byte_perm(sa.x, sbq.x, 0x7632);
          const uint32_t s2 = __byte_perm(sa.y, sbq.y, 0x5410), s3 = __byte_perm(sa.y, sbq.y, 0x7632);
          const uint32_t* kp = (const uint32_t*)(p.k + (size_t)t0 * DM + d0);
          const uint32_t* vp = (const uint32_t*)(p.v + (size_t)t0 * DM + d0);
          uint32_t km3 = 0, km2 = 0, km1 = 0;
          if (t0 > 0) { km3 = ldg_stream(kp - 3 * (DM / 2), pol); km2 = ldg_stream(kp - 2 * (DM / 2), pol); km1 = ldg_stream(kp - (DM / 2), pol); }
#pragma unroll
          for (int hf = 0; hf < 2; hf++) {
            uint32_t kk[8], vv[8];
#pragma unroll
            for (int i = 0; i < 8; i++) { kk[i] = ldg_stream(kp + (hf * 8 + i) * (DM / 2), pol); vv[i] = ldg_stream(vp + (hf * 8 + i) * (DM / 2), pol); }
            uint32_t o[8];
#pragma unroll
            for (int i = 0; i < 8; i++) {
              uint32_t a = bmul2(km3, s3);
              a = badd2(a, bmul2(km2, s2));
              a = badd2(a, bmul2(km1, s1));
              a = badd2(a, bmul2(kk[i], s0));
              o[i] = bmul2(a, vv[i]);
              km3 = km2; km2 = km1; km1 = kk[i];
            }
            uint4 lo, hi;
            lo.x = __byte_perm(o[0], o[1], 0x5410); lo.y = __byte_perm(o[2], o[3], 0x5410); lo.z = __byte_perm(o[4], o[5], 0x5410); lo.w = __byte_perm(o[6], o[7], 0x5410);
            hi.x = __byte_perm(o[0], o[1], 0x7632); hi.y = __byte_perm(o[2], o[3], 0x7632); hi.z = __byte_perm(o[4], o[5], 0x7632); hi.w = __byte_perm(o[6], o[7], 0x7632);
            *(uint4*)(g_kvT + (size_t)d0 * S_LEN + t0 + hf * 8) = lo;
            *(uint4*)(g_kvT + (size_t)(d0 + 1) * S_LEN + t0 + hf * 8) = hi;
          }
        }
        fence_async_all();
        named_bar(4, 96);
        if (warp == 1 && lane == 0) red_release(&g_flags.kv[db], 1);
      }
      if (warp == 3 && lane == 0 && cv_cnt > 0) {
        const unsigned ep = get_ep();
        const int dlo = conv_phys(cv_start) >> 7, dhi = conv_phys(cv_start + cv_cnt - 1) >> 7;
        wait_flag(&g_flags.kv[dlo], 16 * ep);
        wait_flag(&g_flags.kv[dhi], 16 * ep);
        fence_async_all();
        const uint64_t pol = policy_evict_first();
        mbar_wait(bar + B_G1DONE, 0);
        for (int g = 0; g < 2 && g < cv_cnt; g++) {
          const uint32_t base = sb + OFF_CONV + g * CV_WG_BYTES;
          mbar_expect_tx(bar + B_CVH + g * 24, 4096);
          bulk_ld(base + CV_OFF_EX, p.ssm_k + (size_t)conv_phys(cv_start + g) * S_LEN, 4096, bar + B_CVH + g * 24, pol);
          mbar_expect_tx(bar + B_CVF + g * 16, CV_UBYTES);
          tma_ld3(base + CV_OFF_U, &p.uLd, 0, -8, conv_phys(cv_start + g), bar + B_CVF + g * 16, pol);
        }
      }
      if (warp <= 2 && lane == 0) {
        const int wg = warp - 1;
        for (int i = 0; i < n_g1; i++) {
          const int pt = g1_tile(i);
          const int n = pt >> 3, m = 2 * (pt & 7) + rank;
          mbar_wait(bar + B_STF + wg * 8, i & 1);
          uint32_t src = sb + OFF_STG + wg * 16384;
          tma_st2(&p.hSt, src, n * 128, m * 128 + wg * 64);
          tma_st2(&p.hSt, src + 8192, n * 128 + 64, m * 128 + wg * 64);
          bulk_commit();
          bulk_wait_read0();
          mbar_arrive(bar + B_STE + wg * 8);
          if (i == n_g1 - 2) {
            for (int ci = wg; ci < cv_cnt; ci += 2)
              asm volatile("cp.async.bulk.prefetch.L2.global [%0], %1;" ::"l"(p.ssm_k + (size_t)conv_phys(cv_start + ci) * S_LEN), "r"(4096) : "memory");
            if (n_g1 > 2) for (int ci = wg; ci < cv_cnt; ci += 2)
              asm volatile("cp.async.bulk.prefetch.L2.global [%0], %1;" ::"l"(g_kvT + (size_t)conv_phys(cv_start + ci) * S_LEN), "r"(4096) : "memory");
          }
          bulk_wait0();
          fence_async_all();
          red_release(&g_flags.h[m * 32 + n], 1);
        }
        const int nch = (cv_cnt + 1 - wg) >> 1, ch0 = cv_start + wg;
        if (nch > 0) {
          const uint64_t pol = policy_evict_first();
          const uint32_t base = sb + OFF_CONV + wg * CV_WG_BYTES, hraw = sb + OFF_STG + wg * 16384;
          const uint32_t cvb = bar + B_CVF + wg * 16, hvb = bar + B_CVH + wg * 24;
          mbar_wait(bar + B_G1DONE, 0);
          { const unsigned ep = get_ep();
            wait_flag(&g_flags.kv[conv_phys(ch0) >> 7], 16 * ep); wait_flag(&g_flags.kv[conv_phys(ch0 + 2 * (nch - 1)) >> 7], 16 * ep); fence_async_all(); }
          if (nch > 1) {
            mbar_expect_tx(hvb + 8, 4096); bulk_ld(hraw + 4096, p.ssm_k + (size_t)conv_phys(ch0 + 2) * S_LEN, 4096, hvb + 8, pol);
            mbar_expect_tx(cvb + 8, CV_UBYTES); tma_ld3(base + CV_OFF_U + CV_USTRIDE, &p.uLd, 0, -8, conv_phys(ch0 + 2), cvb + 8, pol);
          }
          if (nch > 2) { mbar_expect_tx(hvb + 16, 4096); bulk_ld(hraw, p.ssm_k + (size_t)conv_phys(ch0 + 4) * S_LEN, 4096, hvb + 16, pol); }
          for (int j = 0; j < nch; j++) {
            mbar_wait(bar + B_YFULL + wg * 8, j & 1);
            const int ch = conv_phys(ch0 + 2 * j);
            tma_st3(&p.ySt, hraw + 8192, 0, 0, ch);
            bulk_commit();
            if (j + 2 < nch) { mbar_expect_tx(cvb + (j & 1) * 8, CV_UBYTES); tma_ld3(base + CV_OFF_U + (j & 1) * CV_USTRIDE, &p.uLd, 0, -8, conv_phys(ch0 + 2 * (j + 2)), cvb + (j & 1) * 8, pol); }
            if (j + 3 < nch) {
              const uint32_t hb = hvb + 8 + ((j + 1) & 1 ? 0 : 8);
              mbar_expect_tx(hb, 4096); bulk_ld(hraw + ((j + 1) & 1) * 4096, p.ssm_k + (size_t)conv_phys(ch0 + 2 * (j + 3)) * S_LEN, 4096, hb, pol);
            }
            bulk_wait_read0();
            mbar_arrive(bar + B_OFREE + wg * 8);
          }
          bulk_wait0();
          fence_async_all();
          const int llo = ch0 >> 7, lhi = (ch0 + 2 * (nch - 1)) >> 7;
          if (llo == lhi) red_release(&g_flags.y[conv_phys(ch0) >> 7], nch);
          else {
            const int n1 = ((lhi << 7) - ch0 + 1) >> 1;
            asm volatile("fence.acq_rel.gpu;" ::: "memory");
            asm volatile("red.relaxed.gpu.global.add.u32 [%0], %1;" ::"l"(&g_flags.y[conv_phys(ch0) >> 7]), "r"(n1) : "memory");
            asm volatile("red.relaxed.gpu.global.add.u32 [%0], %1;" ::"l"(&g_flags.y[conv_phys(lhi << 7) >> 7]), "r"(nch - n1) : "memory");
          }
        }
      }
    }
    kernel_tail();
  } else {
    asm volatile("setmaxnreg.inc.sync.aligned.u32 224;");
    const int wg = (warp - 4) >> 2;
    const int w = warp & 3;
    const int tid = threadIdx.x & 127;
    const int r = lane >> 2, c = lane & 3;
    if (bid < 128) {
      const int cw = warp - 4;
      const int row0 = bid * 16 + cw * 2;
      float sm[2] = {0.f, 0.f}, ss[2] = {0.f, 0.f};
#pragma unroll
      for (int rr = 0; rr < 2; rr++)
#pragma unroll
        for (int j = 0; j < 4; j++) {
          const uint32_t* u = (const uint32_t*)&xv[rr][j];
          sm[rr] += ((bf_lo(u[0]) + bf_hi(u[0])) + (bf_lo(u[1]) + bf_hi(u[1]))) + ((bf_lo(u[2]) + bf_hi(u[2])) + (bf_lo(u[3]) + bf_hi(u[3])));
        }
#pragma unroll
      for (int o = 16; o > 0; o >>= 1) { sm[0] += __shfl_xor_sync(0xffffffffu, sm[0], o); sm[1] += __shfl_xor_sync(0xffffffffu, sm[1], o); }
#pragma unroll
      for (int rr = 0; rr < 2; rr++) {
        const float mean = sm[rr] * (1.0f / DM);
        sm[rr] = mean;
        float s0 = 0.f, s1 = 0.f;
#pragma unroll
        for (int j = 0; j < 4; j++) {
          const uint32_t* u = (const uint32_t*)&xv[rr][j];
#pragma unroll
          for (int e = 0; e < 4; e++) { const float a = bf_lo(u[e]) - mean, b = bf_hi(u[e]) - mean; s0 = fmaf(a, a, s0); s1 = fmaf(b, b, s1); }
        }
        ss[rr] = s0 + s1;
      }
#pragma unroll
      for (int o = 16; o > 0; o >>= 1) { ss[0] += __shfl_xor_sync(0xffffffffu, ss[0], o); ss[1] += __shfl_xor_sync(0xffffffffu, ss[1], o); }
#pragma unroll
      for (int rr = 0; rr < 2; rr++) {
        const __nv_bfloat16 mb = __float2bfloat16_rn(sm[rr]);
        const uint32_t mb2 = (uint32_t)__bfloat16_as_ushort(mb) * 0x10001u;
        const float vb = __bfloat162float(__float2bfloat16_rn(ss[rr] * (1.0f / DM)));
        const float tb = __bfloat162float(__float2bfloat16_rn(vb + 1e-5f));
        const float sd = __bfloat162float(__float2bfloat16_rn(sqrtf(tb)));
        const float rs = __frcp_rn(sd);
#pragma unroll
        for (int j = 0; j < 4; j++) {
          const uint32_t* u = (const uint32_t*)&xv[rr][j];
          uint4 o4; uint32_t* o = (uint32_t*)&o4;
#pragma unroll
          for (int e = 0; e < 4; e++) {
            const __nv_bfloat162 d2 = __hsub2_rn(*(const __nv_bfloat162*)&u[e], *(const __nv_bfloat162*)&mb2);
            const uint32_t d = *(const uint32_t*)&d2;
            o[e] = pack_bf16(bf_lo(d) * rs, bf_hi(d) * rs);
          }
          *(uint4*)(g_xn + (size_t)(row0 + rr) * DM + j * 256 + lane * 8) = o4;
        }
      }
      fence_async_all();
      named_bar(3, 256);
      if (warp == 4 && lane == 0) red_release(&g_flags.xn[bid >> 3], 1);
    }
    {
      float acc[128];
      uint32_t gp[32], up[32];
      const uint32_t stg = sb + OFF_STG + wg * 16384;
      const int mi = lane >> 3;
      const int row = 16 * w + (mi & 1) * 8 + (lane & 7);
      const uint32_t stg_row = stg + row * 128;
      auto epi_chunk = [&](int j) {
        uint32_t o[4];
        silu4(gp + 2 * j, o);
#pragma unroll
        for (int q = 0; q < 4; q++) o[q] = bmul2(o[q], up[2 * j + q]);
        const int cb = j + (mi >> 1);
        stsm_x4(stg_row + (cb >> 3) * 8192 + (((cb & 7) ^ (row & 7)) << 4), o);
      };
      for (int i = 0; i < n_g1; i++) {
#pragma unroll
        for (int kb = 0; kb < 16; kb++) {
          const int st = kb & 3;
          mbar_wait(bar + B_G1F + st * 8, (kb >> 2) & 1);
          const uint32_t sa = sb + st * G1_STAGE;
          const uint32_t alo = (((sa + wg * 8192) & 0x3FFFF) >> 4) | (1u << 16);
          const uint32_t blo = (((sa + 16384) & 0x3FFFF) >> 4) | (512u << 16);
          wg_fence();
#pragma unroll
          for (int kk = 0; kk < 4; kk++)
            wgmma_ss_n256(acc, mkd(alo + kk * 2, 0x40000040u), mkd(blo + kk * 128, 0x40000040u), (kb | kk) ? 1 : 0);
          wg_commit();
          if (i > 0 && kb >= 1 && kb <= 8) {
            if (kb == 1 && i > 1) mbar_wait(bar + B_STE + wg * 8, (i - 2) & 1);
            epi_chunk(2 * (kb - 1));
            if (kb == 8) { fence_async_smem(); mbar_arrive(bar + B_STF + wg * 8); }
          }
          wg_wait<1>();
          if (kb > 0 && tid == 0 && (kb <= 12 || i + 1 < n_g1 || (has_g2 && kb <= 14))) { mbar_arrive(bar + B_G1E + ((kb - 1) & 3) * 8); mbar_arrive_remote(bar + B_G1E + ((kb - 1) & 3) * 8, rank ^ 1); }
        }
        wg_wait<0>();
        if (tid == 0) {
          if (i + 1 < n_g1) { mbar_arrive(bar + B_G1E + 3 * 8); mbar_arrive_remote(bar + B_G1E + 3 * 8, rank ^ 1); }
          else mbar_arrive(bar + B_G1DONE);
        }
#pragma unroll
        for (int j = 0; j < 16; j++) {
          gp[2 * j] = pack_bf16(acc[4 * j], acc[4 * j + 1]); gp[2 * j + 1] = pack_bf16(acc[4 * j + 2], acc[4 * j + 3]);
          up[2 * j] = pack_bf16(acc[64 + 4 * j], acc[64 + 4 * j + 1]); up[2 * j + 1] = pack_bf16(acc[64 + 4 * j + 2], acc[64 + 4 * j + 3]);
        }
      }
      mbar_wait(bar + B_G1DONE, 0);
      if (n_g1 > 1) mbar_wait(bar + B_STE + wg * 8, (n_g1 - 2) & 1);
#pragma unroll
      for (int j = 0; j < 16; j += 2) epi_chunk(j);
      fence_async_smem();
      mbar_arrive(bar + B_STF + wg * 8);
    }
    {
      const int nch = (cv_cnt + 1 - wg) >> 1;
      if (nch > 0) {
        const uint32_t base = sb + OFF_CONV + wg * CV_WG_BYTES;
        const uint32_t cvb = bar + B_CVF + wg * 16;
        const int ch0 = cv_start + wg;
        const uint32_t hraw = sb + OFF_STG + wg * 16384;
        const uint32_t obuf = hraw + 8192;
        const uint32_t hvb = bar + B_CVH + wg * 24;
        if (tid < 64) asm volatile("st.shared.b32 [%0], %1;" ::"r"(base + CV_OFF_Q + (tid >> 5) * CV_QSZ + (((tid & 31) >> 2) * QP + (tid & 3)) * 4), "r"(0) : "memory");
        if (tid >= 64 && tid - 64 < nch) {
          const unsigned short dd = __ldg((const unsigned short*)(p.ssm_D + conv_phys(ch0 + 2 * (tid - 64))));
          asm volatile("st.shared.b32 [%0], %1;" ::"r"(base + CV_OFF_D + (tid - 64) * 4), "r"((uint32_t)dd | ((uint32_t)dd << 16)) : "memory");
        }
        asm volatile("st.shared.b32 [%0], %1;" ::"r"(base + CV_OFF_EX + 42 * 512 + tid * 4), "r"(0) : "memory");
        const int v = r - 2 * c;
        const int rho = v & 7, ib = 16 * w + (v < 0 ? -1 : 0);
        const uint32_t qaddr0 = base + CV_OFF_Q + (rho * QP + ib + 3) * 4;
        const uint32_t exl = base + CV_OFF_EX + lane * 16;
        const uint32_t zero = p.zero;
        mbar_wait(hvb, 0);
        conv_build_q(base + CV_OFF_Q, base + CV_OFF_EX, tid);
        named_bar(1 + wg, 128);
        uint32_t aX[8][4], aY[8][4];
        float own[16];
        { uint32_t t[17]; conv_load_t<0>(t, qaddr0); conv_expand_a(aX, t, zero); }
        mbar_wait(cvb, 0);
        auto finalize = [&](int it) {
          const uint32_t ub = base + CV_OFF_U + (it & 1) * CV_USTRIDE;
          named_bar(1 + wg, 128);
          conv_recv(exl, w, own);
          if (it > 0) mbar_wait(bar + B_OFREE + wg * 8, (it - 1) & 1);
          else mbar_wait(bar + B_STE + wg * 8, (n_g1 - 1) & 1);
          const uint32_t d2 = lds32(base + CV_OFF_D + it * 4);
#pragma unroll
          for (int q = 0; q < 2; q++) {
            const int mi = lane >> 3;
            const int pp = 8 * (4 * w + 2 * q + (mi >> 1)) + (lane & 7);
            const uint32_t urow = pp + 8;
            uint32_t uu[4], oo[4];
            ldsm_x4_t(ub + urow * 32 + (((mi & 1) ^ ((urow >> 2) & 1)) << 4), uu);
#pragma unroll
            for (int k = 0; k < 4; k++) oo[k] = badd2(pack_bf16(own[8 * q + 2 * k], own[8 * q + 2 * k + 1]), bmul2(uu[k], d2));
            stsm_x4_t(obuf + pp * 32 + (((mi & 1) ^ ((pp >> 2) & 1)) << 4), oo);
          }
          fence_async_smem();
          mbar_arrive(bar + B_YFULL + wg * 8);
        };
        for (int it = 0; it < nch; it++) {
          const int buf = it & 1;
          const uint32_t ubase = base + CV_OFF_U + buf * CV_USTRIDE;
          const uint32_t ulo = ((ubase & 0x3FFFF) >> 4) | (1u << 16);
          const uint32_t qaddr = qaddr0 + buf * CV_QSZ;
          const bool more = it + 1 < nch;
          float c0[64], c1[48], c2[32], c3[16];
          uint32_t t[17];
          conv_load_t<1>(t, qaddr);
          wg_fence(); conv_group<0>(c0, aX, ulo); wg_commit();
          conv_expand_a(aY, t, zero);
          if (it > 0) finalize(it - 1);
          wg_wait<0>();
          conv_load_t<2>(t, qaddr);
          CPY(c1, c0, 16, 48); wg_fence(); conv_group<1>(c1, aY, ulo); wg_commit();
          conv_expand_a(aX, t, zero);
          if (more) {
            mbar_wait(hvb + (buf ? 16 : 8), (it >> 1) & 1);
            conv_build_q(base + CV_OFF_Q + (buf ^ 1) * CV_QSZ, hraw + (buf ^ 1) * 4096, tid);
          }
          wg_wait<0>();
          conv_load_t<3>(t, qaddr);
          CPY(c2, c1, 16, 32); wg_fence(); conv_group<2>(c2, aX, ulo); wg_commit();
          conv_expand_a(aY, t, zero);
          named_bar(1 + wg, 128);
          wg_wait<0>();
          if (more) conv_load_t<0>(t, qaddr0 + (buf ^ 1) * CV_QSZ);
          CPY(c3, c2, 16, 16); wg_fence(); conv_group<3>(c3, aY, ulo); wg_commit();
          if (more) { conv_expand_a(aX, t, zero); mbar_wait(cvb + (buf ^ 1) * 8, ((it + 1) >> 1) & 1); }
          wg_wait<0>();
          if (w == 0) conv_send<0>(c0, c1, c2, c3, exl, own, zero); else if (w == 1) conv_send<1>(c0, c1, c2, c3, exl, own, zero);
          else if (w == 2) conv_send<2>(c0, c1, c2, c3, exl, own, zero); else conv_send<3>(c0, c1, c2, c3, exl, own, zero);
        }
        finalize(nch - 1);
      }
    }
    if (has_g2) {
      if (tid == 0) {
        for (int s = 2; s < 4; s++) { mbar_arrive(bar + B_G1E + s * 8); mbar_arrive_remote(bar + B_G1E + s * 8, rank ^ 1); }
      }
      float acc[128];
      for (int k4 = 0; k4 < G2_KB / 4; k4++) {
#pragma unroll
        for (int st = 0; st < 4; st++) {
          mbar_wait(bar + B_G1F + st * 8, k4 & 1);
          const uint32_t sa = sb + st * G1_STAGE;
          const uint32_t alo = (((sa + wg * 8192) & 0x3FFFF) >> 4) | (1u << 16);
          const uint32_t blo = (((sa + 16384) & 0x3FFFF) >> 4) | (512u << 16);
          wg_fence();
#pragma unroll
          for (int kk = 0; kk < 4; kk++)
            wgmma_ss_n256(acc, mkd(alo + kk * 2, 0x40000040u), mkd(blo + kk * 128, 0x40000040u), (k4 | st | kk) ? 1 : 0);
          wg_commit();
          wg_wait<1>();
          if ((k4 | st) && tid == 0) { mbar_arrive(bar + B_G1E + ((st + 3) & 3) * 8); mbar_arrive_remote(bar + B_G1E + ((st + 3) & 3) * 8, rank ^ 1); }
        }
      }
      wg_wait<0>();
      if (tid == 0) { mbar_arrive(bar + B_G1E + 3 * 8); mbar_arrive_remote(bar + B_G1E + 3 * 8, rank ^ 1); }
      const int mi = lane >> 3;
      const int trow = 64 * wg + 16 * w + (mi & 1) * 8 + (lane & 7);
#pragma unroll
      for (int hf = 0; hf < 2; hf++) {
        const uint32_t sx = sb + (2 * hf) * G1_STAGE, sn = sb + (2 * hf + 1) * G1_STAGE;
        const uint32_t sy = (wg == 0 ? sx : sn) + 32768;
        mbar_wait(bar + B_G1F + (2 * hf) * 8, (G2_KB / 4) & 1);
        mbar_wait(bar + B_G1F + (2 * hf + 1) * 8, (G2_KB / 4) & 1);
#pragma unroll
        for (int jb = 0; jb < 16; jb += 8) {
          uint32_t xr[4][4], sr[4][4], g[4][4];
#pragma unroll
          for (int u = 0; u < 4; u++) {
            const int cb = jb + 2 * u + (mi >> 1);
            const uint32_t off = (cb >> 3) * 16384 + trow * 128 + (((cb & 7) ^ (trow & 7)) << 4);
            uint32_t nr[4], yr[4];
            ldsm_x4(sn + off, nr);
            const int drow = 8 * cb + (lane & 7);
            const int tch = 2 * w + (mi & 1);
            ldsm_x4_t(sy + drow * 128 + ((tch ^ (drow & 7)) << 4), yr);
            ldsm_x4(sx + off, xr[u]);
#pragma unroll
            for (int q = 0; q < 4; q++) sr[u][q] = bmul2(nr[q], yr[q]);
          }
#pragma unroll
          for (int u = 0; u < 4; u++) {
            uint32_t fb[4];
#pragma unroll
            for (int q = 0; q < 4; q++) { const int b = 64 * hf + 4 * (jb + 2 * u + (q >> 1)) + 2 * (q & 1); fb[q] = pack_bf16(acc[b], acc[b + 1]); }
            silu4(fb, g[u]);
          }
#pragma unroll
          for (int u = 0; u < 4; u++) {
            const int cb = jb + 2 * u + (mi >> 1);
            const uint32_t off = (cb >> 3) * 16384 + trow * 128 + (((cb & 7) ^ (trow & 7)) << 4);
            uint32_t o[4];
#pragma unroll
            for (int q = 0; q < 4; q++) o[q] = badd2(xr[u][q], bmul2(sr[u][q], g[u][q]));
            stsm_x4(sx + off, o);
          }
        }
        __syncwarp();
        {
          const int rl = lane >> 4, ck = lane & 15;
          __nv_bfloat16* op = out + (size_t)(g2_m * 128 + 64 * wg + 16 * w + rl) * DM + g2_n * 256 + hf * 128 + ck * 8;
#pragma unroll
          for (int ps = 0; ps < 8; ps++) {
            const int rw = 64 * wg + 16 * w + 2 * ps + rl;
            uint4 v4;
            asm volatile("ld.shared.v4.b32 {%0, %1, %2, %3}, [%4];" : "=r"(v4.x), "=r"(v4.y), "=r"(v4.z), "=r"(v4.w)
                         : "r"(sx + (ck >> 3) * 16384 + rw * 128 + (((ck & 7) ^ (rw & 7)) << 4)) : "memory");
            *(uint4*)(op + (size_t)(2 * ps) * DM) = v4;
          }
        }
      }
    }
    kernel_tail();
  }
}

typedef CUresult (*EncodeFn)(CUtensorMap*, CUtensorMapDataType, cuuint32_t, void*, const cuuint64_t*, const cuuint64_t*, const cuuint32_t*,
                             const cuuint32_t*, CUtensorMapInterleave, CUtensorMapSwizzle, CUtensorMapL2promotion, CUtensorMapFloatOOBfill);

void make2d(EncodeFn enc, CUtensorMap* m, const void* ptr, uint64_t inner, uint64_t outer, uint32_t bi, uint32_t bo) {
  cuuint64_t dims[2] = {inner, outer}; cuuint64_t strides[1] = {inner * 2}; cuuint32_t box[2] = {bi, bo}; cuuint32_t es[2] = {1, 1};
  enc(m, CU_TENSOR_MAP_DATA_TYPE_BFLOAT16, 2, (void*)ptr, dims, strides, box, es, CU_TENSOR_MAP_INTERLEAVE_NONE, CU_TENSOR_MAP_SWIZZLE_128B,
      CU_TENSOR_MAP_L2_PROMOTION_L2_128B, CU_TENSOR_MAP_FLOAT_OOB_FILL_NONE);
}
void make3d(EncodeFn enc, CUtensorMap* m, const void* ptr, uint32_t rows) {
  cuuint64_t dims[3] = {16, 128, (cuuint64_t)DM}; cuuint64_t strides[2] = {32, 4096}; cuuint32_t box[3] = {16, rows, 1}; cuuint32_t es[3] = {1, 1, 1};
  enc(m, CU_TENSOR_MAP_DATA_TYPE_BFLOAT16, 3, (void*)ptr, dims, strides, box, es, CU_TENSOR_MAP_INTERLEAVE_NONE, CU_TENSOR_MAP_SWIZZLE_32B,
      CU_TENSOR_MAP_L2_PROMOTION_NONE, CU_TENSOR_MAP_FLOAT_OOB_FILL_NONE);
}

}

extern "C" void kernel_launch(void* const* d_in, const int* in_sizes, int n_in, void* d_out, int out_size) {
  (void)in_sizes; (void)n_in; (void)out_size;
  static EncodeFn enc = nullptr;
  static void *a_xn, *a_kv, *a_y, *a_h;
  if (!enc) {
    void* fn = nullptr; cudaDriverEntryPointQueryResult st;
    cudaGetDriverEntryPoint("cuTensorMapEncodeTiled", &fn, cudaEnableDefault, &st);
    enc = (EncodeFn)fn;
    cudaGetSymbolAddress(&a_xn, g_xn); cudaGetSymbolAddress(&a_kv, g_kvT); cudaGetSymbolAddress(&a_y, g_yT); cudaGetSymbolAddress(&a_h, g_H);
    cudaFuncSetAttribute(h3_ffn_kernel, cudaFuncAttributeMaxDynamicSharedMemorySize, SMEM_BYTES);
  }
  Params p;
  p.q = (const __nv_bfloat16*)d_in[0]; p.k = (const __nv_bfloat16*)d_in[1]; p.v = (const __nv_bfloat16*)d_in[2];
  p.shift_k = (const __nv_bfloat16*)d_in[3]; p.ssm_k = (const __nv_bfloat16*)d_in[4]; p.ssm_D = (const __nv_bfloat16*)d_in[5]; p.zero = 0;
  make2d(enc, &p.xnA, a_xn, DM, S_LEN, 64, 128);
  make2d(enc, &p.wg, d_in[7], FF, DM, 64, 64);
  make2d(enc, &p.wu, d_in[8], FF, DM, 64, 64);
  make2d(enc, &p.hSt, a_h, FF, S_LEN, 64, 64);
  make2d(enc, &p.hA, a_h, FF, S_LEN, 64, 128);
  make2d(enc, &p.wd, d_in[9], DM, FF, 64, 64);
  make3d(enc, &p.uLd, a_kv, CV_UROWS);
  make3d(enc, &p.ySt, a_y, 128);
  make2d(enc, &p.xEp, d_in[0], DM, S_LEN, 64, 128);
  make2d(enc, &p.yEp, a_y, S_LEN, DM, 64, 128);
  make2d(enc, &p.oSt, d_out, DM, S_LEN, 64, 64);
  h3_ffn_kernel<<<NCTA, 384, SMEM_BYTES, cudaStreamPerThread>>>(p, (__nv_bfloat16*)d_out);
}
```
